```python
import torch

def _softmax(x, axis=-1):
    return torch.softmax(x, dim=axis)
def _gelu(x):
    return torch.nn.functional.gelu(x, approximate="tanh")
def _silu(x):
    return torch.nn.functional.silu(x)
def _sigmoid(x):
    return torch.sigmoid(x)
def _layernorm(x, axis=-1, eps=1e-5):
    m = x.mean(dim=axis, keepdim=True)
    v = x.var(dim=axis, keepdim=True, unbiased=False)
    return (x - m) / torch.sqrt(v + eps)
def _scatter_add(tgt, idx, src, axis=0):
    return tgt.clone().index_add_(axis, idx, src)
def _segment_sum(src, seg, n):
    out = torch.zeros((n,) + src.shape[1:], dtype=src.dtype)
    return out.index_add_(0, seg, src)
def _pad(x, pw):
    flat = tuple(v for pair in reversed(pw) for v in pair)
    return torch.nn.functional.pad(x, flat)

kernel_name = 'standalone__rezero__prompt'

def setup_inputs():

    _w = (lambda a: (lambda t: t.to(torch.bfloat16) if t.is_floating_point() else t)(torch.as_tensor(a)))
    B, S, D = 4, 2048, 448
    return {
        "x": _w((lambda *s: torch.randn(*s, dtype=torch.bfloat16) * 0.05)(B, S, D)),
        "fx": _w((lambda *s: torch.randn(*s, dtype=torch.bfloat16) * 0.4)(B, S, D)),
        "alpha": _w((lambda *s: torch.randn(*s, dtype=torch.bfloat16) * 0.4)(1) * 0.1),
    }

def reference(x, fx, alpha):
    return x + alpha * fx
```

```cpp
#include <cuda_runtime.h>
#include <cuda_bf16.h>
#include <stdint.h>

__device__ __forceinline__ uint32_t rezero2(uint32_t x, uint32_t f, __nv_bfloat162 a) {
    __nv_bfloat162 xv = *reinterpret_cast<__nv_bfloat162*>(&x);
    __nv_bfloat162 fv = *reinterpret_cast<__nv_bfloat162*>(&f);
    __nv_bfloat162 r = __hadd2_rn(xv, __hmul2_rn(a, fv));
    return *reinterpret_cast<uint32_t*>(&r);
}

__global__ void __launch_bounds__(256)
rezero_vec_kernel(const uint4* __restrict__ x, const uint4* __restrict__ fx,
                  const __nv_bfloat16* __restrict__ alpha, uint4* __restrict__ out, int nvec) {
    int i = blockIdx.x * 256 + threadIdx.x;
    if (i >= nvec) return;
    uint4 xv = x[i];
    uint4 fv = fx[i];
    __nv_bfloat162 a = __bfloat162bfloat162(alpha[0]);
    uint4 o;
    o.x = rezero2(xv.x, fv.x, a);
    o.y = rezero2(xv.y, fv.y, a);
    o.z = rezero2(xv.z, fv.z, a);
    o.w = rezero2(xv.w, fv.w, a);
    out[i] = o;
}

__global__ void rezero_tail_kernel(const __nv_bfloat16* __restrict__ x, const __nv_bfloat16* __restrict__ fx,
                                   const __nv_bfloat16* __restrict__ alpha, __nv_bfloat16* __restrict__ out,
                                   int start, int n) {
    int i = start + blockIdx.x * blockDim.x + threadIdx.x;
    if (i < n) out[i] = __hadd_rn(x[i], __hmul_rn(alpha[0], fx[i]));
}

extern "C" void kernel_launch(void* const* d_in, const int* in_sizes, int n_in,
                              void* d_out, int out_size) {
    const __nv_bfloat16* x = (const __nv_bfloat16*)d_in[0];
    const __nv_bfloat16* fx = (const __nv_bfloat16*)d_in[1];
    const __nv_bfloat16* alpha = (const __nv_bfloat16*)d_in[2];
    __nv_bfloat16* out = (__nv_bfloat16*)d_out;
    int n = out_size;
    int nvec = n / 8;
    if (nvec > 0)
        rezero_vec_kernel<<<(nvec + 255) / 256, 256>>>((const uint4*)x, (const uint4*)fx, alpha, (uint4*)out, nvec);
    if (nvec * 8 < n)
        rezero_tail_kernel<<<1, 32>>>(x, fx, alpha, out, nvec * 8, n);
}
```

```cpp
#include <cuda_runtime.h>
#include <cuda_bf16.h>
#include <stdint.h>

namespace {

constexpr int kThreads = 512;
constexpr int kRounds = 4;

__device__ __forceinline__ uint4 ld_stream(const uint4* p) {
    uint4 v;
    asm volatile("ld.global.nc.L1::no_allocate.v4.u32 {%0,%1,%2,%3}, [%4];"
                 : "=r"(v.x), "=r"(v.y), "=r"(v.z), "=r"(v.w)
                 : "l"(p));
    return v;
}

__device__ __forceinline__ void st_vec(uint4* p, uint4 v) {
    asm volatile("st.global.v4.u32 [%0], {%1,%2,%3,%4};"
                 :
                 : "l"(p), "r"(v.x), "r"(v.y), "r"(v.z), "r"(v.w)
                 : "memory");
}

__device__ __forceinline__ uint32_t rezero2(uint32_t x, uint32_t f, __nv_bfloat162 a) {
    __nv_bfloat162 xv = *reinterpret_cast<__nv_bfloat162*>(&x);
    __nv_bfloat162 fv = *reinterpret_cast<__nv_bfloat162*>(&f);
    __nv_bfloat162 r = __hadd2_rn(xv, __hmul2_rn(a, fv));
    return *reinterpret_cast<uint32_t*>(&r);
}

__global__ void __launch_bounds__(kThreads)
rezero_vec_kernel(const uint4* __restrict__ x, const uint4* __restrict__ fx,
                  const __nv_bfloat16* __restrict__ alpha, uint4* __restrict__ out, int nvec) {
    const int stride = gridDim.x * kThreads;
    const __nv_bfloat162 a = __bfloat162bfloat162(alpha[0]);
#pragma unroll 1
    for (int i = blockIdx.x * kThreads + threadIdx.x; i < nvec; i += stride) {
        const uint4 xv = ld_stream(x + i);
        const uint4 fv = ld_stream(fx + i);
        uint4 o;
        o.x = rezero2(xv.x, fv.x, a);
        o.y = rezero2(xv.y, fv.y, a);
        o.z = rezero2(xv.z, fv.z, a);
        o.w = rezero2(xv.w, fv.w, a);
        st_vec(out + i, o);
    }
}

__global__ void rezero_scalar_kernel(const __nv_bfloat16* __restrict__ x,
                                     const __nv_bfloat16* __restrict__ fx,
                                     const __nv_bfloat16* __restrict__ alpha,
                                     __nv_bfloat16* __restrict__ out, int start, int n) {
    const __nv_bfloat16 a = alpha[0];
    const long long step = (long long)gridDim.x * blockDim.x;
    for (long long i = (long long)start + blockIdx.x * blockDim.x + threadIdx.x; i < n; i += step)
        out[i] = __hadd_rn(x[i], __hmul_rn(a, fx[i]));
}

}

extern "C" void kernel_launch(void* const* d_in, const int* in_sizes, int n_in,
                              void* d_out, int out_size) {
    const __nv_bfloat16* x = (const __nv_bfloat16*)d_in[0];
    const __nv_bfloat16* fx = (const __nv_bfloat16*)d_in[1];
    const __nv_bfloat16* alpha = (const __nv_bfloat16*)d_in[2];
    __nv_bfloat16* out = (__nv_bfloat16*)d_out;
    const int n = out_size;

    int dev = 0, sms = 132;
    cudaGetDevice(&dev);
    cudaDeviceGetAttribute(&sms, cudaDevAttrMultiProcessorCount, dev);

    const bool aligned = ((((uintptr_t)x) | ((uintptr_t)fx) | ((uintptr_t)out)) & 15u) == 0;
    const int nvec = aligned ? n / 8 : 0;
    if (nvec > 0) {
        const int blocks = (nvec + kThreads - 1) / kThreads;
        int grid = (blocks + kRounds - 1) / kRounds;
        if (grid < sms) grid = blocks < sms ? blocks : sms;
        if (grid > 2 * sms) grid = 2 * sms;
        rezero_vec_kernel<<<grid, kThreads>>>((const uint4*)x, (const uint4*)fx, alpha,
                                              (uint4*)out, nvec);
    }
    const int done = nvec * 8;
    if (done < n) {
        const int rem = n - done;
        int grid = (rem + 255) / 256;
        if (grid > 8 * sms) grid = 8 * sms;
        rezero_scalar_kernel<<<grid, 256>>>(x, fx, alpha, out, done, n);
    }
}
```
